```python
import torch

def _softmax(x, axis=-1):
    return torch.softmax(x, dim=axis)
def _gelu(x):
    return torch.nn.functional.gelu(x, approximate="tanh")
def _silu(x):
    return torch.nn.functional.silu(x)
def _sigmoid(x):
    return torch.sigmoid(x)
def _layernorm(x, axis=-1, eps=1e-5):
    m = x.mean(dim=axis, keepdim=True)
    v = x.var(dim=axis, keepdim=True, unbiased=False)
    return (x - m) / torch.sqrt(v + eps)
def _scatter_add(tgt, idx, src, axis=0):
    return tgt.clone().index_add_(axis, idx, src)
def _segment_sum(src, seg, n):
    out = torch.zeros((n,) + src.shape[1:], dtype=src.dtype)
    return out.index_add_(0, seg, src)
def _pad(x, pw):
    flat = tuple(v for pair in reversed(pw) for v in pair)
    return torch.nn.functional.pad(x, flat)

kernel_name = 'gated_mix__mha_block__glu_gated_bilinear__prompt'

def setup_inputs():

    _w = (lambda a: (lambda t: t.to(torch.bfloat16) if t.is_floating_point() else t)(torch.as_tensor(a)))
    def _A_setup():
        B, S, D, H = 1, 2048, 512, 32
        return {
            "x": _w((lambda *s: torch.randn(*s, dtype=torch.bfloat16) * 0.05)(B, S, D)),
            "wqkv": _w((lambda *s: torch.randn(*s, dtype=torch.bfloat16) * 0.8)(D, 3 * D)),
            "wo": _w((lambda *s: torch.randn(*s, dtype=torch.bfloat16) * 0.05)(D, D)),
        }
    _A_in = _A_setup()

    def _B_setup():
        B, S, D, F = 1, 2048, 512, 1376
        return {
            "x": _w((lambda *s: torch.randn(*s, dtype=torch.bfloat16) * 0.05)(B, S, D)),
            "w_gate": _w((lambda *s: torch.randn(*s, dtype=torch.bfloat16) * 1.6)(D, F) * (D ** -0.5)),
            "w_up": _w((lambda *s: torch.randn(*s, dtype=torch.bfloat16) * 1.6)(D, F) * (D ** -0.5)),
            "w_down": _w((lambda *s: torch.randn(*s, dtype=torch.bfloat16) * 1.6)(F, D) * (F ** -0.5)),
        }
    _B_in = _B_setup()

    return {
        "A_x": _A_in["x"],
        "A_wqkv": _A_in["wqkv"],
        "A_wo": _A_in["wo"],
        "B_x": _B_in["x"],
        "B_w_gate": _B_in["w_gate"],
        "B_w_up": _B_in["w_up"],
        "B_w_down": _B_in["w_down"],
        "gate_w": _w((lambda *s: torch.randn(*s, dtype=torch.bfloat16) * 0.05)(512) * 16.0),
    }

def reference(A_x, A_wqkv, A_wo, B_x, B_w_gate, B_w_up, B_w_down, gate_w):
    def _A_ref(x, wqkv, wo):
        B, S, D = x.shape
        H = 32
        Dh = D // H
        qkv = (lambda x, *d: x.permute(*d))((x @ wqkv).reshape(B, S, 3, H, Dh), 2, 0, 3, 1, 4)
        q, k, v = qkv[0], qkv[1], qkv[2]
        scores = torch.einsum("bhqd,bhkd->bhqk", q, k) * (Dh ** -0.5)
        p = _softmax(scores, axis=-1)
        o = torch.einsum("bhqk,bhkd->bhqd", p, v)
        return (lambda x, *d: x.permute(*d))(o, 0, 2, 1, 3).reshape(B, S, D) @ wo

    def _B_ref(x, w_gate, w_up, w_down):
        g = torch.einsum("bsd,df->bsf", x, w_gate)
        u = torch.einsum("bsd,df->bsf", x, w_up)
        h = g * u
        return torch.einsum("bsf,fd->bsd", h, w_down)

    x = A_x
    g = _sigmoid((x * gate_w).sum(-1, keepdims=True))
    a = _A_ref(x, A_wqkv, A_wo)
    b = _B_ref(x, B_w_gate, B_w_up, B_w_down)
    return g * a + (1 - g) * b
```

```cpp
#include <cuda_runtime.h>
#include <cuda.h>
#include <cuda_bf16.h>
#include <cuda_fp16.h>
#include <stdint.h>

#define ALUM 0xb4
#define PATA 0x49
#define PATB 0x49
extern "C" { extern __shared__ __align__(1024) uint8_t dsmem[]; }
namespace {

constexpr int S_ = 2048, D_ = 512, F_ = 1376;
constexpr int NCTA = 128;
constexpr int VGRP = 272;
constexpr int VHEAD = 256 * VGRP;

__device__ __align__(1024) uint8_t g_Q[32 * 65536];
__device__ __align__(1024) uint8_t g_K[32 * 65536];
__device__ __align__(1024) uint8_t g_V16[32 * VHEAD];
__device__ __align__(1024) uint8_t g_H[32 * 172 * 1024];
__device__ __align__(1024) uint8_t g_O[32 * 64 * 1024];
__device__ float g_gate[S_];
__device__ int g_vok[8];
__device__ unsigned g_cnt[320];
#define TS(i)
#define TSP(i)

constexpr int SM_X = 0;
constexpr int SM_RING = 131072;
constexpr int SLOT = 24576;
constexpr int SM_Q = 0;
constexpr int SM_KV = 16384;
constexpr int KVCH = 8192 + 32 * VGRP;
constexpr int SM_DR = SM_RING + SLOT;
constexpr int DSLOT = 36864;
constexpr int SM_WO = SM_KV;
__host__ __device__ constexpr int sm_ot(int i) { return SM_DR + (i < 4 ? DSLOT + i * 8192 : (i - 4) * 8192); }
constexpr int SM_BAR = SM_RING + 4 * SLOT;
constexpr int SM_ORD = SM_BAR + 448;
constexpr int SM_VOK = SM_BAR + 480;
constexpr int SMEM_BYTES = SM_BAR + 512;
static_assert(SM_KV + 8 * KVCH + 128 <= SM_DR, "attention operands overlap the down ring");
enum {
  B_FULL = 0, B_EMPTY = 4, B_XFULL = 8, B_KV = 16, B_FIN = 19, B_DFULL = 20, B_DEMPTY = 22, B_WO = 24, B_OT = 32,
  B_XFREE = 40, B_GATE = 41, B_SIGA = 42, B_SIGB = 43, B_SIGO = 44, B_ATT = 45, B_COUNT = 46
};

constexpr long long WAIT_LIMIT = 1ll << 28;
__device__ __forceinline__ uint32_t rd_smem() { uint32_t v; asm volatile("mov.u32 %0, dsmem;" : "=r"(v)); return v; }
__device__ __forceinline__ int rd_cta() { int v; asm volatile("mov.u32 %0, %%ctaid.x;" : "=r"(v)); return v; }
__device__ __forceinline__ int rd_tid() { int v; asm volatile("mov.u32 %0, %%tid.x;" : "=r"(v)); return v; }
__device__ __forceinline__ void mbar_init(uint32_t a, uint32_t c) { asm volatile("mbarrier.init.shared::cta.b64 [%0], %1;" :: "r"(a), "r"(c) : "memory"); }
__device__ __forceinline__ void mbar_expect(uint32_t a, uint32_t b) { asm volatile("mbarrier.arrive.expect_tx.shared::cta.b64 _, [%0], %1;" :: "r"(a), "r"(b) : "memory"); }
__device__ __forceinline__ void mbar_arrive(uint32_t a) { asm volatile("mbarrier.arrive.shared::cta.b64 _, [%0];" :: "r"(a) : "memory"); }
__device__ __forceinline__ bool mbar_try(uint32_t a, uint32_t ph) {
  uint32_t ok;
  asm volatile("{.reg .pred p; mbarrier.try_wait.parity.shared::cta.b64 p, [%1], %2; selp.u32 %0, 1, 0, p;}" : "=r"(ok) : "r"(a), "r"(ph) : "memory");
  return ok;
}
__device__ __forceinline__ bool mbar_try_long(uint32_t a, uint32_t ph) {
  uint32_t ok;
  asm volatile("{.reg .pred p; mbarrier.try_wait.parity.shared::cta.b64 p, [%1], %2, %3; selp.u32 %0, 1, 0, p;}" : "=r"(ok) : "r"(a), "r"(ph), "r"(100000u) : "memory");
  return ok;
}
__device__ __forceinline__ void mbar_wait(uint32_t a, uint32_t ph) {
  if (mbar_try(a, ph)) return;
  const long long t0 = clock64();
  while (!mbar_try_long(a, ph)) { if (clock64() - t0 > WAIT_LIMIT) break; }
}
__device__ __forceinline__ void mbar_wait_warp(uint32_t a, uint32_t ph) { mbar_wait(a, ph); __syncwarp(); }
__device__ __forceinline__ void flag_wait(const unsigned* p, unsigned target) {
  const long long t0 = clock64();
  while (true) {
    unsigned v;
    asm volatile("ld.acquire.gpu.global.u32 %0, [%1];" : "=r"(v) : "l"(p) : "memory");
    if (v >= target || clock64() - t0 > WAIT_LIMIT) break;
    __nanosleep(20);
  }
  asm volatile("fence.proxy.async.global;" ::: "memory");
}
__device__ __forceinline__ void flag_signal(unsigned* p, unsigned n) {
  asm volatile("fence.acq_rel.gpu;" ::: "memory");
  asm volatile("red.relaxed.gpu.global.add.u32 [%0], %1;" :: "l"(p), "r"(n) : "memory");
}
__device__ __forceinline__ void tma2d(uint32_t dst, const CUtensorMap* m, int c0, int c1, uint32_t bar) {
  asm volatile("cp.async.bulk.tensor.2d.shared::cluster.global.mbarrier::complete_tx::bytes [%0], [%1, {%3, %4}], [%2];"
               :: "r"(dst), "l"(m), "r"(bar), "r"(c0), "r"(c1) : "memory");
}
__device__ __forceinline__ void tma3d(uint32_t dst, const CUtensorMap* m, int c0, int c1, int c2, uint32_t bar) {
  asm volatile("cp.async.bulk.tensor.3d.shared::cluster.global.mbarrier::complete_tx::bytes [%0], [%1, {%3, %4, %5}], [%2];"
               :: "r"(dst), "l"(m), "r"(bar), "r"(c0), "r"(c1), "r"(c2) : "memory");
}
__device__ __forceinline__ void bulk(uint32_t dst, const void* src, uint32_t bytes, uint32_t bar) {
  asm volatile("cp.async.bulk.shared::cluster.global.mbarrier::complete_tx::bytes [%0], [%1], %2, [%3];"
               :: "r"(dst), "l"(src), "r"(bytes), "r"(bar) : "memory");
}
__device__ __forceinline__ void tma2d_mc(uint32_t dst, const CUtensorMap* m, int c0, int c1, uint32_t bar) {
  asm volatile("cp.async.bulk.tensor.2d.shared::cluster.global.mbarrier::complete_tx::bytes.multicast::cluster [%0], [%1, {%3, %4}], [%2], %5;"
               :: "r"(dst), "l"(m), "r"(bar), "r"(c0), "r"(c1), "h"((uint16_t)3) : "memory");
}
__device__ __forceinline__ void tma3d_mc(uint32_t dst, const CUtensorMap* m, int c0, int c1, uint32_t bar) {
  asm volatile("cp.async.bulk.tensor.3d.shared::cluster.global.mbarrier::complete_tx::bytes.multicast::cluster [%0], [%1, {%3, %4, %6}], [%2], %5;"
               :: "r"(dst), "l"(m), "r"(bar), "r"(c0), "r"(c1), "h"((uint16_t)3), "r"(0) : "memory");
}
__device__ __forceinline__ void bulk_mc(uint32_t dst, const void* src, uint32_t bytes, uint32_t bar) {
  asm volatile("cp.async.bulk.shared::cluster.global.mbarrier::complete_tx::bytes.multicast::cluster [%0], [%1], %2, [%3], %4;"
               :: "r"(dst), "l"(src), "r"(bytes), "r"(bar), "h"((uint16_t)3) : "memory");
}
__device__ __forceinline__ void mbar_arrive_pair(uint32_t a, int lane) {
  if (lane < 2) {
    uint32_t r;
    asm volatile("mapa.shared::cluster.u32 %0, %1, %2;" : "=r"(r) : "r"(a), "r"(lane));
    asm volatile("mbarrier.arrive.shared::cluster.b64 _, [%0];" :: "r"(r) : "memory");
  }
}
__device__ __forceinline__ void l2_prefetch(const void* src, uint32_t bytes) {
  asm volatile("cp.async.bulk.prefetch.L2.global [%0], %1;" :: "l"(src), "r"(bytes) : "memory");
}
__device__ __forceinline__ uint64_t make_desc(uint32_t saddr, uint32_t lbo, uint32_t sbo, uint32_t swz) {
  return (uint64_t)((saddr & 0x3FFFF) >> 4) | ((uint64_t)(lbo >> 4) << 16) | ((uint64_t)(sbo >> 4) << 32) | ((uint64_t)swz << 62);
}
constexpr uint32_t SB0 = 1024;
__host__ __device__ constexpr uint64_t cdesc(uint32_t off, uint32_t lbo, uint32_t sbo, uint32_t swz) {
  return (uint64_t)((SB0 + off) >> 4) | ((uint64_t)(lbo >> 4) << 16) | ((uint64_t)(sbo >> 4) << 32) | ((uint64_t)swz << 62);
}
#define WG_FENCE asm volatile("wgmma.fence.sync.aligned;" ::: "memory")
#define WG_COMMIT asm volatile("wgmma.commit_group.sync.aligned;" ::: "memory")
#define WG_WAIT(n) asm volatile("wgmma.wait_group.sync.aligned %0;" :: "n"(n) : "memory")
template <int N> __device__ __forceinline__ void pin(float* x) {
#pragma unroll
  for (int i = 0; i < N; i++) asm volatile("" : "+f"(x[i]) :: "memory");
}
template <int N> __device__ __forceinline__ void pin(uint32_t* x) {
#pragma unroll
  for (int i = 0; i < N; i++) asm volatile("" : "+r"(x[i]) :: "memory");
}
__device__ __forceinline__ void wg_rs_h24(uint32_t* d, uint32_t a0, uint32_t a1, uint32_t a2, uint32_t a3, uint64_t b, int sd) {
  asm volatile("{.reg .pred p; setp.ne.b32 p, %11, 0; wgmma.mma_async.sync.aligned.m64n24k16.f16.f16.f16 "
               "{%0,%1,%2,%3,%4,%5}, {%6,%7,%8,%9}, %10, p, 1, 1, 0;}"
               : "+r"(d[0]),"+r"(d[1]),"+r"(d[2]),"+r"(d[3]),"+r"(d[4]),"+r"(d[5])
               : "r"(a0), "r"(a1), "r"(a2), "r"(a3), "l"(b), "r"(sd));
}
__device__ __forceinline__ void wg_rs_n128_tb(float* d, uint32_t a0, uint32_t a1, uint32_t a2, uint32_t a3, uint64_t b, int sd) {
  asm volatile("{.reg .pred p; setp.ne.b32 p, %69, 0; wgmma.mma_async.sync.aligned.m64n128k16.f32.bf16.bf16 "
               "{%0,%1,%2,%3,%4,%5,%6,%7,%8,%9,%10,%11,%12,%13,%14,%15,%16,%17,%18,%19,%20,%21,%22,%23,%24,%25,%26,%27,%28,%29,%30,%31,%32,%33,%34,%35,%36,%37,%38,%39,%40,%41,%42,%43,%44,%45,%46,%47,%48,%49,%50,%51,%52,%53,%54,%55,%56,%57,%58,%59,%60,%61,%62,%63}, {%64,%65,%66,%67}, %68, p, 1, 1, 1;}"
               : "+f"(d[0]),"+f"(d[1]),"+f"(d[2]),"+f"(d[3]),"+f"(d[4]),"+f"(d[5]),"+f"(d[6]),"+f"(d[7]),"+f"(d[8]),"+f"(d[9]),"+f"(d[10]),"+f"(d[11]),"+f"(d[12]),"+f"(d[13]),"+f"(d[14]),"+f"(d[15]),"+f"(d[16]),"+f"(d[17]),"+f"(d[18]),"+f"(d[19]),"+f"(d[20]),"+f"(d[21]),"+f"(d[22]),"+f"(d[23]),"+f"(d[24]),"+f"(d[25]),"+f"(d[26]),"+f"(d[27]),"+f"(d[28]),"+f"(d[29]),"+f"(d[30]),"+f"(d[31]),"+f"(d[32]),"+f"(d[33]),"+f"(d[34]),"+f"(d[35]),"+f"(d[36]),"+f"(d[37]),"+f"(d[38]),"+f"(d[39]),"+f"(d[40]),"+f"(d[41]),"+f"(d[42]),"+f"(d[43]),"+f"(d[44]),"+f"(d[45]),"+f"(d[46]),"+f"(d[47]),"+f"(d[48]),"+f"(d[49]),"+f"(d[50]),"+f"(d[51]),"+f"(d[52]),"+f"(d[53]),"+f"(d[54]),"+f"(d[55]),"+f"(d[56]),"+f"(d[57]),"+f"(d[58]),"+f"(d[59]),"+f"(d[60]),"+f"(d[61]),"+f"(d[62]),"+f"(d[63])
               : "r"(a0), "r"(a1), "r"(a2), "r"(a3), "l"(b), "r"(sd));
}
__device__ __forceinline__ void wg_rs_n64_tb(float* d, uint32_t a0, uint32_t a1, uint32_t a2, uint32_t a3, uint64_t b, int sd) {
  asm volatile("{.reg .pred p; setp.ne.b32 p, %37, 0; wgmma.mma_async.sync.aligned.m64n64k16.f32.bf16.bf16 "
               "{%0,%1,%2,%3,%4,%5,%6,%7,%8,%9,%10,%11,%12,%13,%14,%15,%16,%17,%18,%19,%20,%21,%22,%23,%24,%25,%26,%27,%28,%29,%30,%31}, {%32,%33,%34,%35}, %36, p, 1, 1, 1;}"
               : "+f"(d[0]),"+f"(d[1]),"+f"(d[2]),"+f"(d[3]),"+f"(d[4]),"+f"(d[5]),"+f"(d[6]),"+f"(d[7]),"+f"(d[8]),"+f"(d[9]),"+f"(d[10]),"+f"(d[11]),"+f"(d[12]),"+f"(d[13]),"+f"(d[14]),"+f"(d[15]),"+f"(d[16]),"+f"(d[17]),"+f"(d[18]),"+f"(d[19]),"+f"(d[20]),"+f"(d[21]),"+f"(d[22]),"+f"(d[23]),"+f"(d[24]),"+f"(d[25]),"+f"(d[26]),"+f"(d[27]),"+f"(d[28]),"+f"(d[29]),"+f"(d[30]),"+f"(d[31])
               : "r"(a0), "r"(a1), "r"(a2), "r"(a3), "l"(b), "r"(sd));
}
__device__ __forceinline__ void wg_rs_n80_tb(float* d, uint32_t a0, uint32_t a1, uint32_t a2, uint32_t a3, uint64_t b, int sd) {
  asm volatile("{.reg .pred p; setp.ne.b32 p, %45, 0; wgmma.mma_async.sync.aligned.m64n80k16.f32.bf16.bf16 "
               "{%0,%1,%2,%3,%4,%5,%6,%7,%8,%9,%10,%11,%12,%13,%14,%15,%16,%17,%18,%19,%20,%21,%22,%23,%24,%25,%26,%27,%28,%29,%30,%31,%32,%33,%34,%35,%36,%37,%38,%39}, {%40,%41,%42,%43}, %44, p, 1, 1, 1;}"
               : "+f"(d[0]),"+f"(d[1]),"+f"(d[2]),"+f"(d[3]),"+f"(d[4]),"+f"(d[5]),"+f"(d[6]),"+f"(d[7]),"+f"(d[8]),"+f"(d[9]),"+f"(d[10]),"+f"(d[11]),"+f"(d[12]),"+f"(d[13]),"+f"(d[14]),"+f"(d[15]),"+f"(d[16]),"+f"(d[17]),"+f"(d[18]),"+f"(d[19]),"+f"(d[20]),"+f"(d[21]),"+f"(d[22]),"+f"(d[23]),"+f"(d[24]),"+f"(d[25]),"+f"(d[26]),"+f"(d[27]),"+f"(d[28]),"+f"(d[29]),"+f"(d[30]),"+f"(d[31]),"+f"(d[32]),"+f"(d[33]),"+f"(d[34]),"+f"(d[35]),"+f"(d[36]),"+f"(d[37]),"+f"(d[38]),"+f"(d[39])
               : "r"(a0), "r"(a1), "r"(a2), "r"(a3), "l"(b), "r"(sd));
}
__device__ __forceinline__ void wg_rs_n96_tb(float* d, uint32_t a0, uint32_t a1, uint32_t a2, uint32_t a3, uint64_t b, int sd) {
  asm volatile("{.reg .pred p; setp.ne.b32 p, %53, 0; wgmma.mma_async.sync.aligned.m64n96k16.f32.bf16.bf16 "
               "{%0,%1,%2,%3,%4,%5,%6,%7,%8,%9,%10,%11,%12,%13,%14,%15,%16,%17,%18,%19,%20,%21,%22,%23,%24,%25,%26,%27,%28,%29,%30,%31,%32,%33,%34,%35,%36,%37,%38,%39,%40,%41,%42,%43,%44,%45,%46,%47}, {%48,%49,%50,%51}, %52, p, 1, 1, 1;}"
               : "+f"(d[0]),"+f"(d[1]),"+f"(d[2]),"+f"(d[3]),"+f"(d[4]),"+f"(d[5]),"+f"(d[6]),"+f"(d[7]),"+f"(d[8]),"+f"(d[9]),"+f"(d[10]),"+f"(d[11]),"+f"(d[12]),"+f"(d[13]),"+f"(d[14]),"+f"(d[15]),"+f"(d[16]),"+f"(d[17]),"+f"(d[18]),"+f"(d[19]),"+f"(d[20]),"+f"(d[21]),"+f"(d[22]),"+f"(d[23]),"+f"(d[24]),"+f"(d[25]),"+f"(d[26]),"+f"(d[27]),"+f"(d[28]),"+f"(d[29]),"+f"(d[30]),"+f"(d[31]),"+f"(d[32]),"+f"(d[33]),"+f"(d[34]),"+f"(d[35]),"+f"(d[36]),"+f"(d[37]),"+f"(d[38]),"+f"(d[39]),"+f"(d[40]),"+f"(d[41]),"+f"(d[42]),"+f"(d[43]),"+f"(d[44]),"+f"(d[45]),"+f"(d[46]),"+f"(d[47])
               : "r"(a0), "r"(a1), "r"(a2), "r"(a3), "l"(b), "r"(sd));
}
__device__ __forceinline__ void wg_ss_n32(float* d, uint64_t a, uint64_t b, int sd) {
  asm volatile("{.reg .pred p; setp.ne.b32 p, %18, 0; wgmma.mma_async.sync.aligned.m64n32k16.f32.bf16.bf16 "
               "{%0,%1,%2,%3,%4,%5,%6,%7,%8,%9,%10,%11,%12,%13,%14,%15}, %16, %17, p, 1, 1, 0, 0;}"
               : "+f"(d[0]),"+f"(d[1]),"+f"(d[2]),"+f"(d[3]),"+f"(d[4]),"+f"(d[5]),"+f"(d[6]),"+f"(d[7]),"+f"(d[8]),"+f"(d[9]),"+f"(d[10]),"+f"(d[11]),"+f"(d[12]),"+f"(d[13]),"+f"(d[14]),"+f"(d[15])
               : "l"(a), "l"(b), "r"(sd));
}
__device__ __forceinline__ void wg_ss_n64_tb(float* d, uint64_t a, uint64_t b, int sd) {
  asm volatile("{.reg .pred p; setp.ne.b32 p, %34, 0; wgmma.mma_async.sync.aligned.m64n64k16.f32.bf16.bf16 "
               "{%0,%1,%2,%3,%4,%5,%6,%7,%8,%9,%10,%11,%12,%13,%14,%15,%16,%17,%18,%19,%20,%21,%22,%23,%24,%25,%26,%27,%28,%29,%30,%31}, %32, %33, p, 1, 1, 0, 1;}"
               : "+f"(d[0]),"+f"(d[1]),"+f"(d[2]),"+f"(d[3]),"+f"(d[4]),"+f"(d[5]),"+f"(d[6]),"+f"(d[7]),"+f"(d[8]),"+f"(d[9]),"+f"(d[10]),"+f"(d[11]),"+f"(d[12]),"+f"(d[13]),"+f"(d[14]),"+f"(d[15]),"+f"(d[16]),"+f"(d[17]),"+f"(d[18]),"+f"(d[19]),"+f"(d[20]),"+f"(d[21]),"+f"(d[22]),"+f"(d[23]),"+f"(d[24]),"+f"(d[25]),"+f"(d[26]),"+f"(d[27]),"+f"(d[28]),"+f"(d[29]),"+f"(d[30]),"+f"(d[31])
               : "l"(a), "l"(b), "r"(sd));
}

__device__ __forceinline__ void ldsm4(uint32_t* r, uint32_t a) {
  asm volatile("ldmatrix.sync.aligned.m8n8.x4.shared.b16 {%0,%1,%2,%3}, [%4];" : "=r"(r[0]), "=r"(r[1]), "=r"(r[2]), "=r"(r[3]) : "r"(a) : "memory");
}
__device__ __forceinline__ float ex2f(float x) { float y; asm("ex2.approx.ftz.f32 %0, %1;" : "=f"(y) : "f"(x)); return y; }
__device__ __forceinline__ uint32_t pack_h(float lo, float hi) { uint32_t d; asm("cvt.rn.f16x2.f32 %0, %1, %2;" : "=r"(d) : "f"(hi), "f"(lo)); return d; }
__device__ __forceinline__ uint32_t pack_bf(float lo, float hi) { uint32_t d; asm("cvt.rn.bf16x2.f32 %0, %1, %2;" : "=r"(d) : "f"(hi), "f"(lo)); return d; }
__device__ __forceinline__ uint32_t movm(uint32_t a) { uint32_t d; asm volatile("movmatrix.sync.aligned.m8n8.trans.b16 %0, %1;" : "=r"(d) : "r"(a)); return d; }
__device__ __forceinline__ void stg32(void* p, uint32_t v) { asm volatile("st.global.u32 [%0], %1;" :: "l"(p), "r"(v) : "memory"); }
__device__ __forceinline__ void stg64(void* p, uint32_t a, uint32_t b) { asm volatile("st.global.v2.u32 [%0], {%1, %2};" :: "l"(p), "r"(a), "r"(b) : "memory"); }
__device__ __forceinline__ float h_lo(uint32_t v) { float f; asm("{.reg .b16 l, h; mov.b32 {l, h}, %1; cvt.f32.f16 %0, l;}" : "=f"(f) : "r"(v)); return f; }
__device__ __forceinline__ float h_hi(uint32_t v) { float f; asm("{.reg .b16 l, h; mov.b32 {l, h}, %1; cvt.f32.f16 %0, h;}" : "=f"(f) : "r"(v)); return f; }

__device__ __forceinline__ uint32_t exp2_pair_fma(float s0, float s1, uint32_t z, bool alu) {
  const float mul = __uint_as_float(1024u), add = __uint_as_float(15u * 1024u + 2u);
  const float y0 = __fmaf_rn(s0, mul, add), y1 = __fmaf_rn(s1, mul, add);
  uint32_t I, t, d;
  asm("cvt.pack.sat.s16.s32 %0, %1, %2;" : "=r"(I) : "r"(__float_as_int(y1)), "r"(__float_as_int(y0)));
  const uint32_t k = I & 0x03FF03FFu;
  asm("fma.rn.f16x2 %0, %1, %2, %3;" : "=r"(t) : "r"(k), "r"(0xED5BED5Bu), "r"(0x35773577u));
  asm("mul.rn.f16x2 %0, %1, %2;" : "=r"(d) : "r"(t), "r"(k));
  return alu ? I - d + z : I - d;
}
template <int I0, int PAT>
__device__ __forceinline__ void exp_quad(const float* S, uint32_t* P, uint32_t z) {
#pragma unroll
  for (int i = I0; i < I0 + 4; i++) {
    if ((PAT >> i) & 1) P[i] = pack_h(ex2f(S[2 * i]), ex2f(S[2 * i + 1]));
    else P[i] = exp2_pair_fma(S[2 * i], S[2 * i + 1], z, (ALUM >> i) & 1);
  }
}

__device__ __forceinline__ void mma_bf16(float* d, uint32_t a0, uint32_t a1, uint32_t a2, uint32_t a3, uint32_t b0, uint32_t b1) {
  asm volatile("mma.sync.aligned.m16n8k16.row.col.f32.bf16.bf16.f32 {%0,%1,%2,%3}, {%4,%5,%6,%7}, {%8,%9}, {%0,%1,%2,%3};"
               : "+f"(d[0]), "+f"(d[1]), "+f"(d[2]), "+f"(d[3]) : "r"(a0), "r"(a1), "r"(a2), "r"(a3), "r"(b0), "r"(b1));
}

__device__ __forceinline__ void attn_exact(const uint8_t* gq, const uint8_t* gk, const __nv_bfloat16* x,
                                           const unsigned short* wv, uint8_t* dst) {
  const int lane = threadIdx.x & 31, g = lane >> 2, t = lane & 3;
  const uint32_t* qa = (const uint32_t*)gq + lane;
  const uint32_t q0 = __ldcg(qa), q1 = __ldcg(qa + 64), q2 = __ldcg(qa + 32), q3 = __ldcg(qa + 96);
  float o[8] = {0, 0, 0, 0, 0, 0, 0, 0}, m0 = -INFINITY, m1 = -INFINITY, l0 = 0.f, l1 = 0.f;
  const int tok0 = 8 * ((g >> 1) & 1) + 2 * (g >> 2) + (g & 1);
#pragma unroll 1
  for (int ks = 0; ks < 128; ks++) {
    float s[8] = {0, 0, 0, 0, 0, 0, 0, 0}, v[8] = {0, 0, 0, 0, 0, 0, 0, 0};
    const uint32_t* xa = (const uint32_t*)(x + (ks * 16 + tok0) * D_) + t;
#pragma unroll 2
    for (int kk = 0; kk < 32; kk++) {
      const unsigned short* wp = wv + (kk * 16 + 2 * t) * (3 * D_) + g;
      const uint32_t a0 = wp[0] | ((uint32_t)wp[3 * D_] << 16), a1 = wp[8] | ((uint32_t)wp[3 * D_ + 8] << 16);
      const uint32_t a2 = wp[24 * D_] | ((uint32_t)wp[27 * D_] << 16), a3 = wp[24 * D_ + 8] | ((uint32_t)wp[27 * D_ + 8] << 16);
      mma_bf16(v, a0, a1, a2, a3, xa[kk * 8], xa[kk * 8 + 4]);
      mma_bf16(v + 4, a0, a1, a2, a3, xa[2 * D_ + kk * 8], xa[2 * D_ + kk * 8 + 4]);
    }
    const uint32_t* ka = (const uint32_t*)(gk + ks * 512) + lane;
    mma_bf16(s, q0, q1, q2, q3, __ldcg(ka), __ldcg(ka + 32));
    mma_bf16(s + 4, q0, q1, q2, q3, __ldcg(ka + 64), __ldcg(ka + 96));
    float a = fmaxf(fmaxf(s[0], s[1]), fmaxf(s[4], s[5])), b = fmaxf(fmaxf(s[2], s[3]), fmaxf(s[6], s[7]));
    a = fmaxf(a, __shfl_xor_sync(~0u, a, 1)); a = fmaxf(a, __shfl_xor_sync(~0u, a, 2));
    b = fmaxf(b, __shfl_xor_sync(~0u, b, 1)); b = fmaxf(b, __shfl_xor_sync(~0u, b, 2));
    const float n0 = fmaxf(m0, a), n1 = fmaxf(m1, b);
    const float c0 = exp2f(m0 - n0), c1 = exp2f(m1 - n1);
    m0 = n0; m1 = n1;
    s[0] = exp2f(s[0] - n0); s[1] = exp2f(s[1] - n0); s[4] = exp2f(s[4] - n0); s[5] = exp2f(s[5] - n0);
    s[2] = exp2f(s[2] - n1); s[3] = exp2f(s[3] - n1); s[6] = exp2f(s[6] - n1); s[7] = exp2f(s[7] - n1);
    l0 = l0 * c0 + (s[0] + s[1]) + (s[4] + s[5]);
    l1 = l1 * c1 + (s[2] + s[3]) + (s[6] + s[7]);
    o[0] *= c0; o[1] *= c0; o[4] *= c0; o[5] *= c0; o[2] *= c1; o[3] *= c1; o[6] *= c1; o[7] *= c1;
    const uint32_t p0 = pack_bf(s[0], s[1]), p1 = pack_bf(s[2], s[3]), p2 = pack_bf(s[4], s[5]), p3 = pack_bf(s[6], s[7]);
    mma_bf16(o, p0, p1, p2, p3, pack_bf(v[0], v[1]), pack_bf(v[4], v[5]));
    mma_bf16(o + 4, p0, p1, p2, p3, pack_bf(v[2], v[3]), pack_bf(v[6], v[7]));
  }
  l0 += __shfl_xor_sync(~0u, l0, 1); l0 += __shfl_xor_sync(~0u, l0, 2);
  l1 += __shfl_xor_sync(~0u, l1, 1); l1 += __shfl_xor_sync(~0u, l1, 2);
  const float r0 = 1.f / l0, r1 = 1.f / l1;
  stg32(dst, pack_bf(o[0] * r0, o[1] * r0));
  stg32(dst + 128, pack_bf(o[2] * r1, o[3] * r1));
  stg32(dst + 1024, pack_bf(o[4] * r0, o[5] * r0));
  stg32(dst + 1024 + 128, pack_bf(o[6] * r1, o[7] * r1));
}

__global__ void __cluster_dims__(2, 1, 1) __launch_bounds__(640, 1)
fused_kernel(const __grid_constant__ CUtensorMap tm_x, const __grid_constant__ CUtensorMap tm_wqkv,
             const __grid_constant__ CUtensorMap tm_wg, const __grid_constant__ CUtensorMap tm_wu,
             const __grid_constant__ CUtensorMap tm_wd, const __grid_constant__ CUtensorMap tm_wo,
             const __nv_bfloat16* __restrict__ x, const __nv_bfloat16* __restrict__ gate_w,
             const uint8_t* __restrict__ wqkv, const uint8_t* __restrict__ wg, const uint8_t* __restrict__ wu,
             const uint8_t* __restrict__ wd, const uint8_t* __restrict__ wo,
             __nv_bfloat16* __restrict__ out) {
  {
    const uint32_t sb = (uint32_t)__cvta_generic_to_shared(dsmem);
    auto B = [&](int i) { return sb + SM_BAR + 8 * i; };
    if ((sb & 0x3FFFF) != SB0) return;
    const int c = blockIdx.x;
    const int w = __shfl_sync(~0u, (int)(threadIdx.x >> 7), 0);
    const int warp = __shfl_sync(~0u, (int)((threadIdx.x >> 5) & 3), 0);
    const int lane = threadIdx.x & 31;
    const int j1 = (c >> 1) & 7, r1 = ((c >> 4) << 1) | (c & 1);
    const int f0 = j1 < 6 ? 176 * j1 : 1056 + 160 * (j1 - 6);
    if (threadIdx.x == 512) {
      mbar_init(B(B_XFULL), 1);
      mbar_init(B(B_FULL), 1);
      asm volatile("fence.mbarrier_init.release.cluster;" ::: "memory");
      mbar_expect(B(B_XFULL), 16384);
      tma2d(sb + SM_X, &tm_x, 0, r1 * 128, B(B_XFULL));
      {
        mbar_expect(B(B_FULL), SLOT);
        tma3d(sb + SM_RING, &tm_wqkv, j1 * 64, 0, 0, B(B_FULL));
        tma3d(sb + SM_RING + 12288, &tm_wqkv, j1 * 64, 32, 0, B(B_FULL));
      }
    }
    if (threadIdx.x == 544) {
#pragma unroll
      for (int i = 1; i < B_COUNT; i++) {
        uint32_t cnt = 1;
        if ((i >= B_EMPTY && i < B_XFULL) || i == B_DEMPTY || i == B_DEMPTY + 1 || i == B_XFREE || i == B_ATT) cnt = 16;
        if (i == B_GATE) cnt = 16;
        if (i == B_SIGA) cnt = 256;
        if (i == B_SIGB) cnt = 264;
        if (i == B_SIGO) cnt = 512;
        if (i == B_FIN || i == B_KV) cnt = 2;
        if (i == B_KV + 2) cnt = 5;
        if (i != B_XFULL) mbar_init(B(i), cnt);
      }
      asm volatile("fence.mbarrier_init.release.cluster;" ::: "memory");
    }
    __syncthreads();
    asm volatile("barrier.cluster.arrive.relaxed.aligned; barrier.cluster.wait.aligned;" ::: "memory");

    if (w < 2) {
      asm volatile("setmaxnreg.inc.sync.aligned.u32 200;");
      TS(0);
    {
      float acc[96], p1[96], p2[80];
      uint32_t af[2][16];
      const uint32_t xa = sb + SM_X + (w * 64 + warp * 16 + (lane & 15)) * 128, xs = (lane >> 4) ^ (lane & 7);
#define LOAD_A(kb) do { _Pragma("unroll") for (int k = 0; k < 4; k++) ldsm4(af[(kb) & 1] + 4 * k, xa + ((kb) & 7) * 16384 + (((2 * k) ^ xs) << 4)); } while (0)
#define AF(k) af[kb & 1][4 * (k)], af[kb & 1][4 * (k) + 1], af[kb & 1][4 * (k) + 2], af[kb & 1][4 * (k) + 3]
#define DONE_PREV(kb) do { if ((kb) > 0) { WG_WAIT(1); pin<16>(af[((kb) & 1) ^ 1]); mbar_arrive_pair(B(B_EMPTY + (((kb) - 1) & 3)), lane); } } while (0)
      mbar_wait_warp(B(B_XFULL), 0);
      LOAD_A(0);
#pragma unroll
      for (int kb = 0; kb < 8; kb++) {
        const int s = kb & 3;
        mbar_wait_warp(B(B_FULL + s), (kb >> 2) & 1);
        if (kb == 0) TS(15);
        const uint64_t db = cdesc(SM_RING, 4096, 1024, 1) + s * (SLOT / 16);
        WG_FENCE;
#pragma unroll
        for (int k = 0; k < 4; k++) {
          wg_rs_n128_tb(acc, AF(k), db + (k >> 1) * 768 + (k & 1) * 128, kb | k);
          wg_rs_n64_tb(acc + 64, AF(k), db + 512 + (k >> 1) * 768 + (k & 1) * 128, kb | k);
        }
        WG_COMMIT;
        DONE_PREV(kb);
        if (kb < 7) mbar_wait_warp(B(B_XFULL + kb + 1), 0);
        LOAD_A(kb + 1);
      }
      WG_WAIT(0);
      pin<96>(acc); pin<16>(af[1]);
      mbar_arrive_pair(B(B_EMPTY + 3), lane);
      TS(1);
      uint32_t pk[48];
      const float qs = 0.25f * 1.4426950408889634f;
#pragma unroll
      for (int i = 0; i < 16; i++) {
        const int e = (i >> 2) * 8 + (i & 1) * 4 + (i & 2);
        pk[i] = pack_bf(acc[e] * qs, acc[e + 1] * qs);
        pk[16 + i] = pack_bf(acc[32 + e], acc[33 + e]);
        pk[32 + i] = movm(pack_h(acc[64 + 2 * i], acc[65 + 2 * i]));
      }
      pin<48>(pk);
      const int tg = r1 * 16 + w * 8 + warp * 2;
      const int g = lane >> 2, tq = lane & 3;
      uint8_t* const qp = g_Q + j1 * 4 * 65536 + tg * 256 + (tq >> 1) * 128 + g * 16 + (tq & 1) * 8;
      uint8_t* const kp = g_K + j1 * 4 * 65536 + (tg + (g >> 2)) * 256 + (tq >> 1) * 128 + (4 * ((g >> 1) & 1) + (g & 1)) * 16 + (tq & 1) * 8;
      uint8_t* const vp = g_V16 + j1 * 4 * VHEAD + (tg + (tq >> 1)) * VGRP + g * 16 + (tq & 1) * 8;
      mbar_wait_warp(B(B_FULL), 0);
#pragma unroll
      for (int kb = 0; kb < 8; kb++) {
        const int s = kb & 3;
        const int hh = kb >> 1;
        if (kb & 1) {
          stg64(qp + hh * 65536, pk[4 * hh], pk[4 * hh + 1]);
          stg64(qp + hh * 65536 + 256, pk[4 * hh + 2], pk[4 * hh + 3]);
          stg64(vp + hh * VHEAD + 128, pk[34 + 4 * hh], pk[35 + 4 * hh]);
        } else {
          stg64(kp + hh * 65536, pk[16 + 4 * hh], pk[17 + 4 * hh]);
          stg64(kp + hh * 65536 + 32, pk[18 + 4 * hh], pk[19 + 4 * hh]);
          stg64(vp + hh * VHEAD, pk[32 + 4 * hh], pk[33 + 4 * hh]);
        }
        if (kb == 0) {
          stg32(g_V16 + (j1 * 4 + (lane >> 3)) * VHEAD + (tg + ((lane >> 2) & 1)) * VGRP + 256 + (lane & 3) * 4, 0x3C003C00u);
          if (r1 == 0 && w == 0 && warp == 0) {
            uint32_t mn = 0x7fff;
#pragma unroll
            for (int u = 0; u < 8; u++) {
              const uint32_t a = pk[32 + 2 * u] & 0x7fff7fffu, b = pk[33 + 2 * u] & 0x7fff7fffu;
              uint32_t m = max(max(a & 0xffff, a >> 16), max(b & 0xffff, b >> 16));
              m = max(m, __shfl_xor_sync(~0u, m, 1)); m = max(m, __shfl_xor_sync(~0u, m, 2));
              mn = min(mn, m);
            }
            const bool ok = __all_sync(~0u, mn >= 0x1400);
            if (lane == 0) g_vok[j1] = ok;
          }
        }
        const uint64_t db = cdesc(SM_RING, 4096, 512, 2) + s * (SLOT / 16);
        WG_FENCE;
#pragma unroll
        for (int k = 0; k < 4; k++) {
          wg_rs_n96_tb(p1, AF(k), db + k * 64, kb | k);
          wg_rs_n96_tb(p1 + 48, AF(k), db + 768 + k * 64, kb | k);
        }
        WG_COMMIT;
        if (kb == 7) mbar_arrive(B(B_SIGA));
        DONE_PREV(kb);
        LOAD_A(kb + 1);
        if (kb < 7) mbar_wait_warp(B(B_FULL + ((kb + 1) & 3)), ((kb + 1) >> 2) & 1);
      }
      WG_WAIT(0);
      pin<96>(p1); pin<16>(af[1]);
      mbar_arrive_pair(B(B_EMPTY + 3), lane);
      TS(2);
#pragma unroll
      for (int i = 0; i < 24; i++) pk[i] = pack_bf(p1[2 * i] * p1[48 + 2 * i], p1[2 * i + 1] * p1[49 + 2 * i]);
      pin<24>(pk);
      uint8_t* hp = g_H + ((r1 * 2 + w) * 172 + (f0 >> 3)) * 1024 + warp * 256 + lane * 4;
      mbar_wait_warp(B(B_FULL), 0);
#pragma unroll
      for (int kb = 0; kb < 8; kb++) {
        const int s = kb & 3;
        if (kb < 6) {
#pragma unroll
          for (int t = 2 * kb; t < 2 * kb + 2; t++) {
            stg32(hp + t * 1024, pk[2 * t]);
            stg32(hp + t * 1024 + 128, pk[2 * t + 1]);
          }
        }
        const uint64_t db = cdesc(SM_RING, 4096, 512, 2) + s * (SLOT / 16);
        WG_FENCE;
#pragma unroll
        for (int k = 0; k < 4; k++) {
          wg_rs_n80_tb(p2, AF(k), db + k * 64, kb | k);
          wg_rs_n80_tb(p2 + 40, AF(k), db + 768 + k * 64, kb | k);
        }
        WG_COMMIT;
        DONE_PREV(kb);
        if (kb < 7) { LOAD_A(kb + 1); mbar_wait_warp(B(B_FULL + ((kb + 1) & 3)), ((kb + 1) >> 2) & 1); }
      }
      WG_WAIT(0);
      pin<80>(p2);
      mbar_arrive_pair(B(B_XFREE), lane);
      TS(3);
#pragma unroll
      for (int i = 0; i < 20; i++) pk[i] = pack_bf(p2[2 * i] * p2[40 + 2 * i], p2[2 * i + 1] * p2[41 + 2 * i]);
      pin<20>(pk);
      asm volatile("setmaxnreg.dec.sync.aligned.u32 112;");
#pragma unroll
      for (int t = 0; t < 10; t++) {
        if (t < 8 || j1 < 6) {
          stg32(hp + (12 + t) * 1024, pk[2 * t]);
          stg32(hp + (12 + t) * 1024 + 128, pk[2 * t + 1]);
        }
      }
      mbar_arrive(B(B_SIGB));
    }
    } else if (w < 4) {
      asm volatile("setmaxnreg.dec.sync.aligned.u32 24;");
      {
        __nanosleep(1500);
#pragma unroll 1
        for (int kb = 0; kb < 8; kb++) mbar_wait(B(B_XFULL + kb), 0);
        const int row = j1 * 16 + (w - 2) * 8 + warp * 2;
        const uint32_t xa = sb + SM_X + (lane >> 2) * 16384 + row * 128;
        float z0 = 0.f, z1 = 0.f;
#pragma unroll 1
        for (int hf = 0; hf < 2; hf++) {
          const uint4 gw = *(const uint4*)(gate_w + lane * 16 + hf * 8);
          uint4 a, b;
          asm volatile("ld.shared.v4.u32 {%0,%1,%2,%3}, [%4];" : "=r"(a.x), "=r"(a.y), "=r"(a.z), "=r"(a.w) : "r"(xa + ((((lane & 3) * 2 + hf) ^ (row & 7)) << 4)) : "memory");
          asm volatile("ld.shared.v4.u32 {%0,%1,%2,%3}, [%4];" : "=r"(b.x), "=r"(b.y), "=r"(b.z), "=r"(b.w) : "r"(xa + 128 + ((((lane & 3) * 2 + hf) ^ ((row + 1) & 7)) << 4)) : "memory");
#define DOT2(z, u, v) z = fmaf(__uint_as_float((u) << 16), __uint_as_float((v) << 16), fmaf(__uint_as_float((u) & 0xffff0000u), __uint_as_float((v) & 0xffff0000u), z))
          DOT2(z0, a.x, gw.x); DOT2(z0, a.y, gw.y); DOT2(z0, a.z, gw.z); DOT2(z0, a.w, gw.w);
          DOT2(z1, b.x, gw.x); DOT2(z1, b.y, gw.y); DOT2(z1, b.z, gw.z); DOT2(z1, b.w, gw.w);
        }
#pragma unroll
        for (int o = 16; o; o >>= 1) { z0 += __shfl_xor_sync(~0u, z0, o); z1 += __shfl_xor_sync(~0u, z1, o); }
        if (lane < 2) g_gate[r1 * 128 + row + lane] = __fdividef(1.f, 1.f + __expf(-(lane ? z1 : z0)));
        __syncwarp();
        if (lane == 0) mbar_arrive(B(B_SIGB));
        mbar_arrive_pair(B(B_GATE), lane);
      }
      if (warp == 0) mbar_wait(B(B_XFREE), 0);
      asm volatile("bar.sync %0, 128;" :: "r"(2 + w) : "memory");
      asm volatile("setmaxnreg.inc.sync.aligned.u32 112;");
    } else {
      asm volatile("setmaxnreg.dec.sync.aligned.u32 32;");
      const int head = c >> 2, qq = c & 3, r2 = ((c >> 3) << 1) | (c & 1);
      if (warp == 0) {
        if (lane == 0) {
          const int rank = c & 1;
        auto x_issue = [&](int kb) {
          mbar_expect(B(B_XFULL + kb), 16384);
          tma2d(sb + SM_X + kb * 16384, &tm_x, kb * 64, r1 * 128, B(B_XFULL + kb));
        };
#pragma unroll 4
        for (int it = 0; it < 8; it++) {
          const uint32_t dst = sb + SM_RING + (it & 3) * SLOT + rank * 12288, fb = B(B_FULL + (it & 3));
          if (it >= 4) mbar_wait(B(B_EMPTY + (it & 3)), 0);
          if (it > 0) {
            mbar_expect(fb, SLOT);
            tma3d_mc(dst, &tm_wqkv, j1 * 64, it * 64 + rank * 32, fb);
          }
          if (it < 7) x_issue(it + 1);
        }
        {
          const CUtensorMap* m = rank ? &tm_wu : &tm_wg;
#pragma unroll 1
          for (int it = 8; it < 24; it++) {
            const uint32_t dst = sb + SM_RING + (it & 3) * SLOT, fb = B(B_FULL + (it & 3));
            mbar_wait(B(B_EMPTY + (it & 3)), ((it >> 2) - 1) & 1);
            mbar_expect(fb, SLOT);
            const int k0 = (it & 7) * 64, n0 = f0 + (it >> 4) * 96;
            tma2d_mc(dst + rank * 12288, m, n0, k0, fb);
            tma2d_mc(dst + rank * 12288 + 4096, m, n0 + 32, k0, fb);
            tma2d_mc(dst + rank * 12288 + 8192, m, n0 + 64, k0, fb);
          }
        }
        mbar_wait(B(B_XFREE), 0);
        flag_wait(&g_cnt[8 + (r2 >> 1)], 8);
#pragma unroll 1
        for (int n = 0; n < 16; n++) {
          if (n >= 2) mbar_wait(B(B_DEMPTY + (n & 1)), ((n >> 1) - 1) & 1);
          if (n < 15) {
            const uint32_t dst = sb + SM_DR + (n & 1) * DSLOT, fb = B(B_DFULL + (n & 1)), ab = n < 14 ? 12288 : 4096;
            mbar_expect(fb, ab + 24576);
            bulk(dst, g_H + (r2 * 172 + n * 12) * 1024, ab, fb);
            tma3d(dst + 12288, &tm_wd, 0, n * 96, c & 6, fb);
          }
          const int kb = n - 9;
          if (kb >= 0) {
            mbar_expect(B(B_WO + kb), 16384);
            tma3d(sb + SM_WO + kb * 16384, &tm_wo, 0, kb * 64, c & 6, B(B_WO + kb));
          }
        }
        mbar_wait(B(B_ATT), 0);
        mbar_expect(B(B_WO + 7), 16384);
        tma3d(sb + SM_WO + 7 * 16384, &tm_wo, 0, 7 * 64, c & 6, B(B_WO + 7));
        }
        __syncwarp();
        const long long t0 = clock64();
        bool todo = lane < 8;
        int base = 0;
        while (base < 8) {
          bool rdy = false;
          if (todo) {
            unsigned v;
            asm volatile("ld.acquire.gpu.global.u32 %0, [%1];" : "=r"(v) : "l"(&g_cnt[64 + r2 * 8 + lane]) : "memory");
            rdy = v >= 4 || clock64() - t0 > WAIT_LIMIT;
          }
          const unsigned m = __ballot_sync(~0u, rdy);
          if (rdy) {
            const int slot = base + __popc(m & ((1u << lane) - 1));
            asm volatile("st.shared.u32 [%0], %1;" :: "r"(sb + SM_ORD + slot * 4), "r"(lane) : "memory");
            asm volatile("fence.proxy.async.global;" ::: "memory");
            if (slot >= 4) mbar_wait(B(B_DEMPTY), 1);
            mbar_expect(B(B_OT + slot), 8192);
            bulk(sb + sm_ot(slot), g_O + (r2 * 64 + lane * 8) * 1024, 8192, B(B_OT + slot));
            todo = false;
          }
          base += __popc(m);
        }
        __syncwarp();
        if (lane == 0) mbar_arrive(B(B_FIN));
      } else if (warp == 1) {
        mbar_wait(B(B_XFULL), 0);
        if (lane == 0) {
          l2_prefetch(wg + c * 11008, 11008);
          l2_prefetch(wu + c * 11008, 11008);
        }
        mbar_wait(B(B_XFULL + 7), 0);
        if (lane == 0) {
          l2_prefetch(wd + c * 11008, 11008);
          l2_prefetch(wo + c * 4096, 4096);
        }
        mbar_wait(B(B_ATT), 0);
        mbar_wait(B(B_FIN), 0);
        unsigned last = 0;
        if (lane == 0) { __threadfence(); last = atomicAdd(&g_cnt[24], 1) == NCTA - 1; __threadfence(); }
        if (__shfl_sync(~0u, last, 0)) {
          for (int i = lane; i < 320; i += 32) g_cnt[i] = 0;
        }
      } else if (warp == 2) {
        if (lane == 0) {
          mbar_wait(B(B_SIGA), 0);
          flag_signal(&g_cnt[j1], 1);
          mbar_wait(B(B_SIGB), 0);
          flag_signal(&g_cnt[8 + r1], 1);
        }
        __syncwarp();
        mbar_wait(B(B_SIGO), 0);
        if (lane < 4) flag_signal(&g_cnt[64 + (qq * 8 + 2 * lane + (1 & (head >> 2))) * 8 + (head >> 2)], 1);
        mbar_wait(B(B_SIGO), 1);
        if (lane < 4) flag_signal(&g_cnt[64 + (qq * 8 + 2 * lane + (1 ^ (1 & (head >> 2)))) * 8 + (head >> 2)], 1);
        __syncwarp();
        if (lane == 0) mbar_arrive(B(B_FIN));
      } else if (lane == 0) {
        const int rank = c & 1;
#pragma unroll 1
        for (int u = 0; u < 4; u++) mbar_wait(B(B_EMPTY + 3), u & 1);
        mbar_wait(B(B_EMPTY + 2), 0);
        flag_wait(&g_cnt[head >> 2], 16);
        asm volatile("st.shared.u32 [%0], %1;" :: "r"(sb + SM_VOK), "r"(__ldcg(&g_vok[head >> 2])) : "memory");
        mbar_wait(B(B_GATE), 0);
#pragma unroll 1
        for (int n = 0; n < 8; n++) {
          if (n >= 1 && n < 5) mbar_wait(B(B_EMPTY + ((n + 2) & 3)), n > 1);
          if (n == 5) mbar_wait(B(B_XFREE), 0);
          const uint32_t dst = sb + SM_KV + n * KVCH, fb = B(B_KV + (n > 1) + (n > 2));
          mbar_expect(fb, KVCH + (n == 0 ? 16384 : 0));
          if (n == 0) bulk(sb + SM_Q, g_Q + c * 16384, 16384, fb);
          if (rank == 0) bulk_mc(dst, g_K + head * 65536 + n * 8192, 8192, fb);
          else bulk_mc(dst + 8192, g_V16 + head * VHEAD + n * 32 * VGRP, 32 * VGRP, fb);
        }
      }
      return;
    }
  }

  float ab[32];
  {
    const uint32_t sb = rd_smem();
    auto B = [&](int i) { return sb + SM_BAR + 8 * i; };
    const int tid = rd_tid(), lane = tid & 31;
    const int wid = __shfl_sync(~0u, tid >> 5, 0), w = wid >> 2, warp = wid & 3;
    const bool elect = lane == 0;
    TS(4);
    float S0[16], S1[16];
    uint32_t P0[8], P1[8], OA[6];
#pragma unroll
    for (int i = 0; i < 32; i++) ab[i] = 0.f;
    pin<32>(ab);
    mbar_wait_warp(B(B_KV), 0);
    TS(5);
    const uint32_t zero = blockIdx.y;
    const uint32_t aoff = SM_DR + (w & 1) * 6144, boff = SM_DR + 12288 + (w >> 1) * 12288 + (w & 1) * 6144;
    uint64_t dha = make_desc(sb + aoff, 1024, 128, 0), dhb = make_desc(sb + boff, 12288, 1024, 1);
    const uint64_t xha = ((SB0 + aoff) ^ (SB0 + aoff + DSLOT)) >> 4, xhb = ((SB0 + boff) ^ (SB0 + boff + DSLOT)) >> 4;
    uint32_t odd = 0, dn = 0, fbar = B(B_DFULL);
#define STEP(i, Sc, Sn, Pc) do { \
        if ((i) == 0) WG_FENCE; \
        wg_ss_n32(Sn, dq, dk + ((i) < 7 ? ((i) + 1) * 64 : KVCH / 16), 0); \
        if (((i) & 1) && (i) < 7 && don) wg_ss_n64_tb(ab, dha + ((i) >> 1) * 128, dhb + ((i) >> 1) * 128, 1); \
        WG_COMMIT; \
        if ((i) == 0 && don) mbar_wait_warp(fbar, dn >> 1); \
        WG_WAIT(2); pin<16>(Sc); pin<8>(Pc); \
        if ((i) == 7 && don && elect) mbar_arrive(fbar + 8 * (B_DEMPTY - B_DFULL)); \
        exp_quad<0, ((i) & 1) ? PATB : PATA>(Sc, Pc, zero); \
        WG_FENCE; wg_rs_h24(OA, Pc[0], Pc[1], Pc[2], Pc[3], dv + (i) * 68, (i) != 0 || odd); \
        exp_quad<4, ((i) & 1) ? PATB : PATA>(Sc, Pc, zero); \
        WG_FENCE; wg_rs_h24(OA, Pc[4], Pc[5], Pc[6], Pc[7], dv + (i) * 68 + 34, 1); \
        WG_COMMIT; } while (0)
#define PASS(HK) do { constexpr bool don = HK; \
        STEP(0, S0, S1, P0); STEP(1, S1, S0, P1); STEP(2, S0, S1, P0); STEP(3, S1, S0, P1); \
        STEP(4, S0, S1, P0); STEP(5, S1, S0, P1); STEP(6, S0, S1, P0); STEP(7, S1, S0, P1); \
        WG_WAIT(0); pin<16>(S0); pin<6>(OA); \
        if (odd) { \
        O[0] += h_lo(OA[0]); O[1] += h_hi(OA[0]); O[2] += h_lo(OA[1]); O[3] += h_hi(OA[1]); \
        O[4] += h_lo(OA[2]); O[5] += h_hi(OA[2]); O[6] += h_lo(OA[3]); O[7] += h_hi(OA[3]); \
        L0 += h_lo(OA[4]); L1 += h_lo(OA[5]); } \
        odd ^= 1; \
        dk += KVCH / 16; dv += KVCH / 16; \
        if (don) { dha ^= xha; dhb ^= xhb; fbar ^= 8; dn++; } } while (0)
#pragma unroll 1
    for (int tile = 0; tile < 2; tile++) {
      float O[8] = {0, 0, 0, 0, 0, 0, 0, 0}, L0 = 0.f, L1 = 0.f;
      const uint64_t dq = make_desc(sb + SM_Q + w * 4096 + (tile ^ (1 & (rd_cta() >> 4))) * 2048, 128, 256, 0);
      uint64_t dk = make_desc(sb + SM_KV, 128, 256, 0), dv = make_desc(sb + SM_KV + 8192, VGRP, 128, 0);
      WG_FENCE; wg_ss_n32(S0, dq, dk, 0); WG_COMMIT; WG_WAIT(0); pin<16>(S0);
      if (tile == 1) TS(12);
      if (tile == 0) {
#pragma unroll 1
        for (int n = 1; n < 3; n++) { PASS(false); mbar_wait_warp(B(B_KV + n), 0); }
        TS(10);
      }
#pragma unroll 1
      for (int n = tile ? 8 : 6; n > 0; n--) PASS(true);
      TS(11 + 2 * tile);
      const int c = rd_cta(), head = c >> 2, qq = c & 3, lane = rd_tid() & 31;
      const float l0 = __shfl_sync(~0u, L0, lane & ~3), l1 = __shfl_sync(~0u, L1, lane & ~3);
      float r0, r1;
      asm("rcp.approx.ftz.f32 %0, %1;" : "=f"(r0) : "f"(l0));
      asm("rcp.approx.ftz.f32 %0, %1;" : "=f"(r1) : "f"(l1));
      const float chk = ((fabsf(O[0]) + fabsf(O[1])) + (fabsf(O[2]) + fabsf(O[3]))) + ((fabsf(O[4]) + fabsf(O[5])) + (fabsf(O[6]) + fabsf(O[7])));
      uint32_t vok;
      asm volatile("ld.shared.u32 %0, [%1];" : "=r"(vok) : "r"(rd_smem() + SM_VOK) : "memory");
      const bool good = vok && fminf(l0, l1) >= 64.f && chk + (l0 + l1) < INFINITY;
      const int rt = tile ^ (1 & (c >> 4));
      uint8_t* dst = g_O + ((qq * 8 + w * 2 + rt) * 64 + head * 2) * 1024 + warp * 256 + lane * 4;
      if (__all_sync(~0u, good)) {
        stg32(dst, pack_bf(O[0] * r0, O[1] * r0));
        stg32(dst + 128, pack_bf(O[2] * r1, O[3] * r1));
        stg32(dst + 1024, pack_bf(O[4] * r0, O[5] * r0));
        stg32(dst + 1024 + 128, pack_bf(O[6] * r1, O[7] * r1));
      } else {
        attn_exact(g_Q + head * 65536 + qq * 16384 + w * 4096 + rt * 2048 + warp * 512, g_K + head * 65536, x,
                   (const unsigned short*)wqkv + 2 * D_ + head * 16, dst);
      }
      mbar_arrive(B(B_SIGO));
    }
    TS(6);
    __syncwarp();
    if (elect) mbar_arrive(B(B_ATT));
    mbar_wait_warp(B(B_DFULL), 1);
    WG_FENCE;
    wg_ss_n64_tb(ab, dha - (w & 1) * 256, dhb - (w & 1) * 256, 1);
    WG_COMMIT; WG_WAIT(0);
    if (elect) mbar_arrive(B(B_DEMPTY));
    pin<32>(ab);
  }
  {
    const uint32_t sb = rd_smem();
    auto B = [&](int i) { return sb + SM_BAR + 8 * i; };
    const int c = rd_cta(), tid = rd_tid(), lane = tid & 31, j2 = (c >> 1) & 3, r2 = ((c >> 3) << 1) | (c & 1);
    const int w = __shfl_sync(~0u, tid >> 7, 0), warp = __shfl_sync(~0u, (tid >> 5) & 3, 0);
    const uint32_t x0 = sb + (tid & 127) * 16 + (w >> 1) * 8192;
    const uint32_t x1 = sb + (tid & 127) * 16 + (w >> 1 ? SM_WO + 131072 : SM_DR + 32768);
    const uint32_t x2 = sb + (tid & 127) * 16 + (w >> 1 ? SM_WO + 131072 + 4096 : SM_DR + DSLOT + 32768);
    asm volatile("bar.sync 1, 512;" ::: "memory");
    if (w & 1) {
#pragma unroll
      for (int t = 0; t < 8; t++)
        asm volatile("st.shared.v4.f32 [%0], {%1,%2,%3,%4};" :: "r"(t < 4 ? x0 + t * 2048 : (t < 6 ? x1 : x2) + (t & 1) * 2048), "f"(ab[4 * t]), "f"(ab[4 * t + 1]), "f"(ab[4 * t + 2]), "f"(ab[4 * t + 3]) : "memory");
      asm volatile("bar.arrive %0, 256;" :: "r"(2 + (w >> 1)) : "memory");
    } else {
      const int row = r2 * 64 + warp * 16 + (lane >> 2);
      const float g0 = __ldcg(&g_gate[row]), g1 = __ldcg(&g_gate[row + 8]);
      asm volatile("bar.sync %0, 256;" :: "r"(2 + (w >> 1)) : "memory");
      float aa[32], bb[32];
#pragma unroll
      for (int t = 0; t < 8; t++) {
        float4 p;
        asm volatile("ld.shared.v4.f32 {%0,%1,%2,%3}, [%4];" : "=f"(p.x), "=f"(p.y), "=f"(p.z), "=f"(p.w) : "r"(t < 4 ? x0 + t * 2048 : (t < 6 ? x1 : x2) + (t & 1) * 2048) : "memory");
        bb[4 * t] = (ab[4 * t] + p.x) * (1.f - g0); bb[4 * t + 1] = (ab[4 * t + 1] + p.y) * (1.f - g0);
        bb[4 * t + 2] = (ab[4 * t + 2] + p.z) * (1.f - g1); bb[4 * t + 3] = (ab[4 * t + 3] + p.w) * (1.f - g1);
      }
      pin<32>(bb);
#pragma unroll
      for (int i = 0; i < 8; i++) {
        mbar_wait_warp(B(B_OT + i), 0);
        int kb;
        asm volatile("ld.shared.u32 %0, [%1];" : "=r"(kb) : "r"(sb + SM_ORD + i * 4) : "memory");
        kb = __shfl_sync(~0u, kb, 0);
        mbar_wait_warp(B(B_WO + kb), 0);
        const uint64_t da = make_desc(sb + sm_ot(i), 1024, 128, 0);
        const uint64_t db = make_desc(sb + SM_WO + kb * 16384 + (w >> 1) * 8192, 8192, 1024, 1);
        WG_FENCE;
#pragma unroll
        for (int k = 0; k < 4; k++) wg_ss_n64_tb(aa, da + k * 128, db + k * 128, i | k);
        WG_COMMIT;
      }
      WG_WAIT(0);
      pin<32>(aa);
      TS(8);
      const uint32_t stg = sb + (w >> 1) * 8192 + warp * 512;
#pragma unroll
      for (int t = 0; t < 8; t += 2) {
        uint32_t r[4];
#pragma unroll
        for (int u = 0; u < 2; u++) {
          const int b = 4 * (t + u);
          r[2 * u] = pack_bf(fmaf(g0, aa[b], bb[b]), fmaf(g0, aa[b + 1], bb[b + 1]));
          r[2 * u + 1] = pack_bf(fmaf(g1, aa[b + 2], bb[b + 2]), fmaf(g1, aa[b + 3], bb[b + 3]));
        }
        const int rr = lane & 15, cc = t + (lane >> 4);
        asm volatile("stmatrix.sync.aligned.m8n8.x4.shared.b16 [%0], {%1,%2,%3,%4};"
                     :: "r"(stg + (rr >> 2) * 2048 + (rr & 3) * 128 + ((cc ^ (rr & 7)) << 4)), "r"(r[0]), "r"(r[1]), "r"(r[2]), "r"(r[3]) : "memory");
      }
      __syncwarp();
#pragma unroll
      for (int i = 0; i < 4; i++) {
        const int rr = i * 4 + (lane >> 3), cc = lane & 7;
        uint4 v;
        asm volatile("ld.shared.v4.u32 {%0,%1,%2,%3}, [%4];" : "=r"(v.x), "=r"(v.y), "=r"(v.z), "=r"(v.w) : "r"(stg + i * 2048 + (rr & 3) * 128 + ((cc ^ (rr & 7)) << 4)) : "memory");
        *(uint4*)(out + (r2 * 64 + warp * 16 + rr) * D_ + j2 * 128 + (w >> 1) * 64 + cc * 8) = v;
      }
      TS(9);
    }
  }
}

typedef CUresult (*EncodeFn)(CUtensorMap*, CUtensorMapDataType, cuuint32_t, void*, const cuuint64_t*, const cuuint64_t*,
                             const cuuint32_t*, const cuuint32_t*, CUtensorMapInterleave, CUtensorMapSwizzle,
                             CUtensorMapL2promotion, CUtensorMapFloatOOBfill);

void make_map(EncodeFn enc, CUtensorMap* m, const void* p, int rows, int cols, int box_rows, int box_cols = 64) {
  cuuint64_t dims[2] = {(cuuint64_t)cols, (cuuint64_t)rows};
  cuuint64_t strides[1] = {(cuuint64_t)cols * 2};
  cuuint32_t box[2] = {(cuuint32_t)box_cols, (cuuint32_t)box_rows};
  cuuint32_t es[2] = {1, 1};
  enc(m, CU_TENSOR_MAP_DATA_TYPE_BFLOAT16, 2, const_cast<void*>(p), dims, strides, box, es, CU_TENSOR_MAP_INTERLEAVE_NONE,
      box_cols == 64 ? CU_TENSOR_MAP_SWIZZLE_128B : CU_TENSOR_MAP_SWIZZLE_64B, CU_TENSOR_MAP_L2_PROMOTION_L2_128B, CU_TENSOR_MAP_FLOAT_OOB_FILL_NONE);
}

void make_map3(EncodeFn enc, CUtensorMap* m, const void* p, int rows, int cols, int box_rows) {
  cuuint64_t dims[3] = {64, (cuuint64_t)rows, (cuuint64_t)cols / 64};
  cuuint64_t strides[2] = {(cuuint64_t)cols * 2, 128};
  cuuint32_t box[3] = {64, (cuuint32_t)box_rows, 2};
  cuuint32_t es[3] = {1, 1, 1};
  enc(m, CU_TENSOR_MAP_DATA_TYPE_BFLOAT16, 3, const_cast<void*>(p), dims, strides, box, es, CU_TENSOR_MAP_INTERLEAVE_NONE,
      CU_TENSOR_MAP_SWIZZLE_128B, CU_TENSOR_MAP_L2_PROMOTION_L2_128B, CU_TENSOR_MAP_FLOAT_OOB_FILL_NONE);
}

}

extern "C" void kernel_launch(void* const* d_in, const int* in_sizes, int n_in, void* d_out, int out_size) {
  (void)in_sizes; (void)n_in; (void)out_size;
  static EncodeFn enc = nullptr;
  if (!enc) {
    void* fn = nullptr;
    cudaDriverEntryPointQueryResult qr;
    cudaGetDriverEntryPoint("cuTensorMapEncodeTiled", &fn, cudaEnableDefault, &qr);
    enc = (EncodeFn)fn;
    cudaFuncSetAttribute(fused_kernel, cudaFuncAttributeMaxDynamicSharedMemorySize, SMEM_BYTES);
  }
  CUtensorMap tx, tqkv, tg, tu, td, to;
  make_map(enc, &tx, d_in[0], S_, D_, 128);
  {
    cuuint64_t dims[3] = {(cuuint64_t)D_, (cuuint64_t)D_, 3}, strides[2] = {3 * D_ * 2, D_ * 2};
    cuuint32_t box[3] = {64, 32, 3}, es[3] = {1, 1, 1};
    enc(&tqkv, CU_TENSOR_MAP_DATA_TYPE_BFLOAT16, 3, d_in[1], dims, strides, box, es, CU_TENSOR_MAP_INTERLEAVE_NONE,
        CU_TENSOR_MAP_SWIZZLE_128B, CU_TENSOR_MAP_L2_PROMOTION_L2_128B, CU_TENSOR_MAP_FLOAT_OOB_FILL_NONE);
  }
  make_map(enc, &tg, d_in[4], D_, F_, 64, 32);
  make_map(enc, &tu, d_in[5], D_, F_, 64, 32);
  make_map3(enc, &td, d_in[6], F_, D_, 96);
  make_map3(enc, &to, d_in[2], D_, D_, 64);
  fused_kernel<<<NCTA, 640, SMEM_BYTES>>>(tx, tqkv, tg, tu, td, to, (const __nv_bfloat16*)d_in[0], (const __nv_bfloat16*)d_in[7],
                                          (const uint8_t*)d_in[1], (const uint8_t*)d_in[4], (const uint8_t*)d_in[5], (const uint8_t*)d_in[6],
                                          (const uint8_t*)d_in[2], (__nv_bfloat16*)d_out);
}
```
